```python
import torch

def _softmax(x, axis=-1):
    return torch.softmax(x, dim=axis)
def _gelu(x):
    return torch.nn.functional.gelu(x, approximate="tanh")
def _silu(x):
    return torch.nn.functional.silu(x)
def _sigmoid(x):
    return torch.sigmoid(x)
def _layernorm(x, axis=-1, eps=1e-5):
    m = x.mean(dim=axis, keepdim=True)
    v = x.var(dim=axis, keepdim=True, unbiased=False)
    return (x - m) / torch.sqrt(v + eps)
def _scatter_add(tgt, idx, src, axis=0):
    return tgt.clone().index_add_(axis, idx, src)
def _segment_sum(src, seg, n):
    out = torch.zeros((n,) + src.shape[1:], dtype=src.dtype)
    return out.index_add_(0, seg, src)
def _pad(x, pw):
    flat = tuple(v for pair in reversed(pw) for v in pair)
    return torch.nn.functional.pad(x, flat)

kernel_name = 'standalone__low_rank_proj_linformer__decode'

def setup_inputs():

    _w = (lambda a: (lambda t: t.to(torch.bfloat16) if t.is_floating_point() else t)(torch.as_tensor(a)))
    B, H, Sq, Skv, Dh, R = 4, 16, 1, 8192, 256, 64
    return {
        "q": _w((lambda *s: torch.randn(*s, dtype=torch.bfloat16) * 0.8)(B, H, Sq, Dh)),
        "k": _w((lambda *s: torch.randn(*s, dtype=torch.bfloat16) * 0.8)(B, H, Skv, Dh)),
        "v": _w((lambda *s: torch.randn(*s, dtype=torch.bfloat16) * 0.05)(B, H, Skv, Dh)),
        "e_proj": _w((lambda *s: torch.randn(*s, dtype=torch.bfloat16) * 0.8)(R, Skv) * (Skv ** -0.5)),
        "f_proj": _w((lambda *s: torch.randn(*s, dtype=torch.bfloat16) * 0.05)(R, Skv) * (Skv ** -0.5)),
    }

def reference(q, k, v, e_proj, f_proj):
    B, H, Sq, Dh = q.shape
    kp = torch.einsum("rn,bhnd->bhrd", e_proj, k)
    vp = torch.einsum("rn,bhnd->bhrd", f_proj, v)
    scores = torch.einsum("bhqd,bhrd->bhqr", q, kp) * (Dh ** -0.5)
    p = _softmax(scores, axis=-1)
    o = torch.einsum("bhqr,bhrd->bhqd", p, vp)
    return o
```

```cpp
#include <cuda_runtime.h>
#include <cuda_bf16.h>
#include <cuda.h>
#include <stdint.h>

#define NSIG 2
#define REPK 2
#define TAILH 4
#define OSTR 288
#define SSTR 288

namespace {

constexpr int BH = 64;
constexpr int SKV = 8192;
constexpr int DH = 256;
constexpr int RK = 64;
constexpr int TROWS = 64;
constexpr int TPB = SKV / TROWS;
constexpr uint32_t KTILES = BH * TPB;
constexpr uint32_t NTILES = 2 * KTILES;
constexpr uint32_t TAIL_T0 = NTILES - TAILH * TPB;
constexpr uint32_t MAIN_BYTES = TROWS * DH * 2;
constexpr uint32_t EF_BYTES = RK * TROWS * 2;
constexpr uint32_t SLOT_BYTES = 41984;
constexpr int FD = 4;
constexpr uint32_t FLUSH_BYTES = 1024;
constexpr uint32_t SMEM_BYTES = 2 * SLOT_BYTES + FD * FLUSH_BYTES + 1024;
constexpr int NTHREADS = 160 + 32 * NSIG;
constexpr uint32_t END_TILE = 0xffffffffu;
constexpr int SPIN_LIMIT = 1 << 22;

__device__ __align__(4096) unsigned int g_ticket[1024];
__device__ __align__(4096) unsigned long long g_ready[512];
__device__ __align__(4096) float g_sacc[BH * (3 * REPK + 1) * SSTR];
__device__ __align__(4096) float g_oacc[BH * 16 * OSTR];
__device__ __align__(4096) uint32_t g_p[BH * 64];

__device__ __forceinline__ float* oword(uint32_t bh, uint32_t w) { return g_oacc + (bh * 16 + (w >> 3)) * OSTR + (w & 7) * 4; }
__device__ __forceinline__ float* sline(uint32_t bh, uint32_t i) { return g_sacc + (bh * (3 * REPK + 1) + i) * SSTR; }

__device__ __forceinline__ uint32_t smem_u32(const void* p) { return (uint32_t)__cvta_generic_to_shared(p); }
__device__ __forceinline__ void mbar_init(uint32_t bar, uint32_t cnt) {
    asm volatile("mbarrier.init.shared::cta.b64 [%0], %1;" ::"r"(bar), "r"(cnt) : "memory");
}
__device__ __forceinline__ void mbar_expect(uint32_t bar, uint32_t bytes) {
    asm volatile("mbarrier.arrive.expect_tx.shared::cta.b64 _, [%0], %1;" ::"r"(bar), "r"(bytes) : "memory");
}
__device__ __forceinline__ void mbar_arrive(uint32_t bar) {
    asm volatile("mbarrier.arrive.shared::cta.b64 _, [%0];" ::"r"(bar) : "memory");
}
__device__ __forceinline__ bool mbar_try(uint32_t bar, uint32_t parity) {
    uint32_t ok;
    asm volatile("{\n.reg .pred p;\nmbarrier.try_wait.parity.shared::cta.b64 p, [%1], %2;\nselp.u32 %0, 1, 0, p;\n}"
                 : "=r"(ok) : "r"(bar), "r"(parity) : "memory");
    return ok;
}
__device__ __forceinline__ void mbar_wait(uint32_t bar, uint32_t parity) {
#pragma unroll 1
    for (int i = 0; i < SPIN_LIMIT; i++)
        if (mbar_try(bar, parity)) return;
    __trap();
}
__device__ __forceinline__ void bulk_load(uint32_t dst, const void* src, uint32_t bytes, uint32_t bar) {
    asm volatile("cp.async.bulk.shared::cluster.global.mbarrier::complete_tx::bytes [%0], [%1], %2, [%3];"
                 ::"r"(dst), "l"(src), "r"(bytes), "r"(bar) : "memory");
}
__device__ __forceinline__ void bulk_load_hint(uint32_t dst, const void* src, uint32_t bytes, uint32_t bar, uint64_t pol) {
    asm volatile("cp.async.bulk.shared::cluster.global.mbarrier::complete_tx::bytes.L2::cache_hint [%0], [%1], %2, [%3], %4;"
                 ::"r"(dst), "l"(src), "r"(bytes), "r"(bar), "l"(pol) : "memory");
}
__device__ __forceinline__ void tma_load_2d(uint32_t dst, const CUtensorMap* map, int c0, int c1, uint32_t bar) {
    asm volatile("cp.async.bulk.tensor.2d.shared::cluster.global.mbarrier::complete_tx::bytes [%0], [%1, {%3, %4}], [%2];"
                 ::"r"(dst), "l"(map), "r"(bar), "r"(c0), "r"(c1) : "memory");
}
__device__ __forceinline__ void ldsm4(uint32_t (&r)[4], uint32_t addr) {
    asm volatile("ldmatrix.sync.aligned.m8n8.x4.shared.b16 {%0,%1,%2,%3}, [%4];"
                 : "=r"(r[0]), "=r"(r[1]), "=r"(r[2]), "=r"(r[3]) : "r"(addr) : "memory");
}
__device__ __forceinline__ void ldsm4t(uint32_t (&r)[4], uint32_t addr) {
    asm volatile("ldmatrix.sync.aligned.m8n8.x4.trans.shared.b16 {%0,%1,%2,%3}, [%4];"
                 : "=r"(r[0]), "=r"(r[1]), "=r"(r[2]), "=r"(r[3]) : "r"(addr) : "memory");
}
__device__ __forceinline__ void mma16816(float (&d)[4], uint32_t a0, uint32_t a1, uint32_t a2, uint32_t a3,
                                         uint32_t b0, uint32_t b1) {
    asm volatile("mma.sync.aligned.m16n8k16.row.col.f32.bf16.bf16.f32 {%0,%1,%2,%3}, {%4,%5,%6,%7}, {%8,%9}, {%0,%1,%2,%3};"
                 : "+f"(d[0]), "+f"(d[1]), "+f"(d[2]), "+f"(d[3])
                 : "r"(a0), "r"(a1), "r"(a2), "r"(a3), "r"(b0), "r"(b1));
}
__device__ __forceinline__ void split_bf16x2(float x0, float x1, uint32_t& hi, uint32_t& lo) {
    asm("cvt.rn.bf16x2.f32 %0, %1, %2;" : "=r"(hi) : "f"(x1), "f"(x0));
    float r0 = x0 - __uint_as_float(hi << 16);
    float r1 = x1 - __uint_as_float(hi & 0xffff0000u);
    asm("cvt.rn.bf16x2.f32 %0, %1, %2;" : "=r"(lo) : "f"(r1), "f"(r0));
}
__device__ __forceinline__ bool arrive_n(float* p, uint32_t n) {
    uint32_t old;
    asm volatile("atom.relaxed.gpu.global.inc.u32 %0, [%1], %2;" : "=r"(old) : "l"(p), "r"(n - 1) : "memory");
    return old == n - 1;
}

__device__ __forceinline__ uint32_t tile_of(uint32_t tk) {
    if (tk < TAIL_T0) return tk;
    const uint32_t r = tk - TAIL_T0;
    return TAIL_T0 + (r % TAILH) * TPB + r / TAILH;
}

struct Bars {
    unsigned long long fullA[2], fullB[2], empty[2], ffull[FD], fempty[FD];
    uint32_t tile[2];
    uint32_t fkey[FD];
};

__device__ __forceinline__ void softmax_head(uint32_t bh, int lane) {
    const float sc = 0.0625f * 1.4426950408889634f;
    unsigned long long raw[REPK];
#pragma unroll
    for (int i = 0; i < REPK; i++)
        asm volatile("atom.relaxed.gpu.global.exch.b64 %0, [%1], 0;" : "=l"(raw[i])
                     : "l"(sline(bh, 3 * i + (lane >> 4)) + (lane & 15) * 2) : "memory");
    float a = 0.f, b = 0.f;
#pragma unroll
    for (int i = 0; i < REPK; i++) { a += __uint_as_float((uint32_t)raw[i]); b += __uint_as_float((uint32_t)(raw[i] >> 32)); }
    a *= sc; b *= sc;
    float m = fmaxf(a, b);
#pragma unroll
    for (int o = 16; o > 0; o >>= 1) m = fmaxf(m, __shfl_xor_sync(0xffffffffu, m, o));
    const float p0 = exp2f(a - m), p1 = exp2f(b - m);
    float sum = p0 + p1;
#pragma unroll
    for (int o = 16; o > 0; o >>= 1) sum += __shfl_xor_sync(0xffffffffu, sum, o);
    const float inv = 1.0f / sum;
    uint32_t hi, lo;
    split_bf16x2(p0 * inv, p1 * inv, hi, lo);
    *reinterpret_cast<uint2*>(g_p + bh * 64 + (lane >> 3) * 16 + (lane & 3) * 4 + ((lane >> 2) & 1) * 2) = make_uint2(hi, lo);
#pragma unroll
    for (int i = 0; i < 4; i++) *reinterpret_cast<float4*>(oword(bh, i * 32 + lane)) = make_float4(0.f, 0.f, 0.f, 0.f);
}

__global__ void __launch_bounds__(NTHREADS, 2)
linformer_decode_kernel(const __grid_constant__ CUtensorMap mapE, const __grid_constant__ CUtensorMap mapF,
                        const __nv_bfloat16* __restrict__ q, const __nv_bfloat16* __restrict__ k,
                        const __nv_bfloat16* __restrict__ v, __nv_bfloat16* __restrict__ out) {
    extern __shared__ unsigned char smem_raw[];
    __shared__ __align__(16) Bars bars;
    const uint32_t sbase = (smem_u32(smem_raw) + 1023u) & ~1023u;
    const uint32_t fbase = sbase + 2 * SLOT_BYTES;
    const int warp = threadIdx.x >> 5, lane = threadIdx.x & 31;
    const uint32_t G = gridDim.x;

    uint64_t pol;
    asm volatile("createpolicy.fractional.L2::evict_first.b64 %0, 1.0;" : "=l"(pol));
    auto issue_aux = [&](uint32_t t, int slot) {
        const uint32_t ph = t >= KTILES;
        const uint32_t bh = (t / TPB) & (BH - 1), j = t % TPB;
        const uint32_t dst = sbase + slot * SLOT_BYTES;
        const uint32_t bB = smem_u32(&bars.fullB[slot]);
        bars.tile[slot] = t;
        mbar_expect(bB, EF_BYTES + (ph ? 256u : 512u));
        tma_load_2d(dst + MAIN_BYTES, ph ? &mapF : &mapE, j * TROWS, 0, bB);
        if (ph) bulk_load(dst + MAIN_BYTES + EF_BYTES, g_p + bh * 64, 256, bB);
        else    bulk_load(dst + MAIN_BYTES + EF_BYTES, q + bh * DH, 512, bB);
    };

    if (threadIdx.x == 128) {
        for (int s = 0; s < 2; s++) {
            mbar_init(smem_u32(&bars.fullA[s]), 1);
            mbar_init(smem_u32(&bars.fullB[s]), 1);
            mbar_init(smem_u32(&bars.empty[s]), 4);
        }
        for (int s = 0; s < FD; s++) {
            mbar_init(smem_u32(&bars.ffull[s]), 4);
            mbar_init(smem_u32(&bars.fempty[s]), 1);
        }
        asm volatile("fence.proxy.async.shared::cta;" ::: "memory");
        mbar_expect(smem_u32(&bars.fullA[0]), MAIN_BYTES);
        bulk_load_hint(sbase, k + (size_t)blockIdx.x * (TROWS * DH), MAIN_BYTES, smem_u32(&bars.fullA[0]), pol);
        issue_aux(blockIdx.x, 0);
    }
    __syncthreads();

    if (warp == 4) {
        if (lane == 0) {
            unsigned long long ready = 0;
            uint32_t tk = G + atomicInc(&g_ticket[0], NTILES - 1);
            for (uint32_t it = 0;; it++) {
                const int slot = (it + 1) & 1;
                if (it >= 1) mbar_wait(smem_u32(&bars.empty[slot]), ((it - 1) >> 1) & 1);
                if (tk >= NTILES) {
                    bars.tile[slot] = END_TILE;
                    mbar_arrive(smem_u32(&bars.fullB[slot]));
                    break;
                }
                const uint32_t cur = tile_of(tk);
                if (cur >= KTILES) {
                    const uint32_t bh = (cur / TPB) & (BH - 1);
                    if (!((ready >> bh) & 1)) {
                        int i = 0;
                        do {
                            asm volatile("ld.acquire.gpu.global.u64 %0, [%1];" : "=l"(ready) : "l"(&g_ready[0]) : "memory");
                            if (++i > SPIN_LIMIT) __trap();
                        } while (!((ready >> bh) & 1));
                        asm volatile("fence.proxy.async.global;" ::: "memory");
                    }
                }
                issue_aux(cur, slot);
                mbar_expect(smem_u32(&bars.fullA[slot]), MAIN_BYTES);
                const __nv_bfloat16* src = (cur >= KTILES ? v : k) + (size_t)(cur & (KTILES - 1)) * (TROWS * DH);
                mbar_wait(smem_u32(&bars.fullA[it & 1]), (it >> 1) & 1);
                bulk_load_hint(sbase + slot * SLOT_BYTES, src, MAIN_BYTES, smem_u32(&bars.fullA[slot]), pol);
                tk = G + atomicInc(&g_ticket[0], NTILES - 1);
            }
        }
    } else if (warp >= 5) {
        for (uint32_t e = warp - 5;; e += NSIG) {
            mbar_wait(smem_u32(&bars.ffull[e % FD]), (e / FD) & 1);
            const uint32_t tl = bars.fkey[e % FD];
            if (tl == END_TILE) break;
            const uint32_t bh = tl / TPB, rep = tl % REPK;
            const uint32_t fb = fbase + (e % FD) * FLUSH_BYTES;
            float sx = 0.f, sy = 0.f;
#pragma unroll
            for (int w = 0; w < 4; w++) {
                float x, y;
                asm volatile("ld.shared.v2.f32 {%0,%1}, [%2];" : "=f"(x), "=f"(y) : "r"(fb + w * 256 + lane * 8) : "memory");
                sx += x; sy += y;
            }
            float r0, r1;
            asm volatile("atom.relaxed.gpu.global.add.v2.f32 {%0,%1}, [%2], {%3,%4};" : "=f"(r0), "=f"(r1)
                         : "l"(sline(bh, 3 * rep + (lane >> 4)) + (lane & 15) * 2), "f"(sx), "f"(sy) : "memory");
            __syncwarp();
            if (lane == 0) mbar_arrive(smem_u32(&bars.fempty[e % FD]));
            if (__ballot_sync(0xffffffffu, (__float_as_uint(r0) ^ __float_as_uint(r1)) == 0x7fb5a3c1u) == 0x5a5a5a5au) __nanosleep(1);
            uint32_t last = 0;
            if (lane == 0 && arrive_n(sline(bh, 3 * rep + 2), TPB / REPK)) last = REPK == 1 || arrive_n(sline(bh, 3 * REPK), REPK);
            if (__shfl_sync(0xffffffffu, last, 0)) {
                softmax_head(bh, lane);
                asm volatile("fence.proxy.async.global;" ::: "memory");
                asm volatile("fence.acq_rel.gpu;" ::: "memory");
                __syncwarp();
                if (lane == 0) atomicOr(&g_ready[0], 1ull << bh);
            }
        }
    } else {
        const int mi = lane >> 3, ri = lane & 7, g = lane >> 2, m = lane & 3;
        const uint32_t e_off = MAIN_BYTES + ((mi & 1) * 8 + ri) * 128 + (((2 * warp + (mi >> 1)) ^ ri) << 4);
        const uint32_t f_off = MAIN_BYTES + ((mi & 1) * 8 + ri) * 128 + (((mi >> 1) ^ ri) << 4);
        const uint32_t k_off = (warp * 16 + (mi & 1) * 8 + ri) * 512 + (mi >> 1) * 128 + ri * 16;
        const uint32_t v_off = ((mi >> 1) * 8 + ri) * 512 + warp * 128 + ((ri ^ ((mi & 1) * 4)) << 4);
        const uint32_t q_off = MAIN_BYTES + EF_BYTES + mi * 128 + ri * 16;
        const int t0 = g ^ (2 * m);
        uint32_t fi = 0;
        bool kdone = false;
        uint32_t pbh = 0;
        float pv0 = 0.f, pv1 = 0.f, pr0 = 0.f, pr1 = 0.f, pr2, prn = -1.f;
        auto settle = [&]() {
            if (prn == (float)(TPB - 1)) {
                __nv_bfloat16* o = out + pbh * DH + warp * 64 + m * 16 + g;
                o[0] = __float2bfloat16(pv0 + pr0);
                o[8] = __float2bfloat16(pv1 + pr1);
                if (threadIdx.x == 0) atomicAnd(&g_ready[0], ~(1ull << pbh));
            }
            prn = -1.f;
        };
        auto stop_score_warps = [&]() {
            for (uint32_t e = fi; e < fi + NSIG; e++) {
                mbar_wait(smem_u32(&bars.fempty[e % FD]), ((e / FD) & 1) ^ 1);
                if (threadIdx.x == 0) bars.fkey[e % FD] = END_TILE;
                __syncwarp();
                if (lane == 0) mbar_arrive(smem_u32(&bars.ffull[e % FD]));
            }
            kdone = true;
        };
        for (uint32_t it = 0;; it++) {
            const int slot = it & 1;
            const uint32_t par = (it >> 1) & 1;
            const uint32_t sb = sbase + slot * SLOT_BYTES;
            mbar_wait(smem_u32(&bars.fullB[slot]), par);
            const uint32_t t = bars.tile[slot];
            if (t < KTILES) {
                uint32_t qf[8][4];
#pragma unroll
                for (int tt = 0; tt < 8; tt++) ldsm4(qf[tt], (sb + q_off) ^ (tt << 4));
                float acc[4][4];
#pragma unroll
                for (int a = 0; a < 4; a++)
#pragma unroll
                    for (int b = 0; b < 4; b++) acc[a][b] = 0.f;
                mbar_wait(smem_u32(&bars.fullA[slot]), par);
#pragma unroll
                for (int tt = 0; tt < 8; tt++) {
                    const uint32_t addr = (sb + k_off) ^ (tt << 4);
#pragma unroll
                    for (int gp = 0; gp < 2; gp++) {
                        uint32_t a[4];
                        ldsm4(a, addr + gp * 256);
                        mma16816(acc[gp * 2 + (tt & 1)], a[0], a[1], a[2], a[3], qf[tt][gp * 2], qf[tt][gp * 2 + 1]);
                    }
                }
                uint32_t ea[4][4];
#pragma unroll
                for (int mt = 0; mt < 4; mt++) ldsm4(ea[mt], sb + e_off + mt * 2048);
                __syncwarp();
                if (lane == 0) mbar_arrive(smem_u32(&bars.empty[slot]));
                float vlo = 0.f, vhi = 0.f;
#pragma unroll
                for (int a = 0; a < 4; a++) {
                    vlo += (g & 1) ? acc[a][1] : acc[a][0];
                    vhi += (g & 1) ? acc[a][3] : acc[a][2];
                }
                const float x0 = __shfl_sync(0xffffffffu, vlo, 9 * m), x1 = __shfl_sync(0xffffffffu, vlo, 9 * m + 4);
                const float x2 = __shfl_sync(0xffffffffu, vhi, 9 * m), x3 = __shfl_sync(0xffffffffu, vhi, 9 * m + 4);
                uint32_t h0, l0, h1, l1;
                split_bf16x2(x0, x1, h0, l0);
                split_bf16x2(x2, x3, h1, l1);
                const uint32_t b0 = g == 0 ? h0 : (g == 1 ? l0 : 0u);
                const uint32_t b1 = g == 0 ? h1 : (g == 1 ? l1 : 0u);
                float sc[4][4];
#pragma unroll
                for (int mt = 0; mt < 4; mt++) {
#pragma unroll
                    for (int b = 0; b < 4; b++) sc[mt][b] = 0.f;
                    mma16816(sc[mt], ea[mt][0], ea[mt][1], ea[mt][2], ea[mt][3], b0, b1);
                }
                const uint32_t fb = fbase + (fi % FD) * FLUSH_BYTES;
                mbar_wait(smem_u32(&bars.fempty[fi % FD]), ((fi / FD) & 1) ^ 1);
                if (m == 0) {
#pragma unroll
                    for (int mt = 0; mt < 4; mt++) {
                        asm volatile("st.shared.f32 [%0], %1;" ::"r"(fb + warp * 256 + (mt * 16 + g) * 4), "f"(sc[mt][0] + sc[mt][1]) : "memory");
                        asm volatile("st.shared.f32 [%0], %1;" ::"r"(fb + warp * 256 + (mt * 16 + g + 8) * 4), "f"(sc[mt][2] + sc[mt][3]) : "memory");
                    }
                }
                if (threadIdx.x == 0) bars.fkey[fi % FD] = t;
                __syncwarp();
                if (lane == 0) mbar_arrive(smem_u32(&bars.ffull[fi % FD]));
                fi++;
                continue;
            }
            if (!kdone) stop_score_warps();
            if (t == END_TILE) break;
            uint32_t wh[4][2], wl[4][2];
            {
                float wacc[8][4];
#pragma unroll
                for (int a = 0; a < 8; a++)
#pragma unroll
                    for (int b = 0; b < 4; b++) wacc[a][b] = 0.f;
#pragma unroll
                for (int ks = 0; ks < 4; ks++) {
                    uint32_t pa[4];
                    asm volatile("ld.shared.v4.u32 {%0,%1,%2,%3}, [%4];" : "=r"(pa[0]), "=r"(pa[1]), "=r"(pa[2]), "=r"(pa[3])
                                 : "r"(sb + MAIN_BYTES + EF_BYTES + ks * 64 + m * 16) : "memory");
#pragma unroll
                    for (int rg = 0; rg < 4; rg++) {
                        uint32_t fq[4];
                        ldsm4t(fq, ((sb + f_off) ^ (rg << 5)) + ks * 2048);
                        mma16816(wacc[2 * rg], pa[0], pa[1], pa[2], pa[3], fq[0], fq[1]);
                        mma16816(wacc[2 * rg + 1], pa[0], pa[1], pa[2], pa[3], fq[2], fq[3]);
                    }
                }
#pragma unroll
                for (int rg = 0; rg < 4; rg++)
#pragma unroll
                    for (int h = 0; h < 2; h++)
                        split_bf16x2(wacc[2 * rg + h][0] + wacc[2 * rg + h][2], wacc[2 * rg + h][1] + wacc[2 * rg + h][3],
                                     wh[rg][h], wl[rg][h]);
            }
            settle();
            float acc[8][4];
#pragma unroll
            for (int a = 0; a < 8; a++)
#pragma unroll
                for (int b = 0; b < 4; b++) acc[a][b] = 0.f;
            mbar_wait(smem_u32(&bars.fullA[slot]), par);
#pragma unroll
            for (int rg = 0; rg < 4; rg++) {
#pragma unroll
                for (int tt = 0; tt < 4; tt++) {
                    const uint32_t mask = (tt == t0 ? 0x0000ffffu : 0u) | (tt == (t0 ^ 1) ? 0xffff0000u : 0u);
                    uint32_t a[4];
                    ldsm4t(a, ((sb + v_off) ^ (tt << 4)) + rg * 8192);
                    mma16816(acc[tt * 2], a[0], a[1], a[2], a[3], wh[rg][0] & mask, wh[rg][1] & mask);
                    mma16816(acc[tt * 2 + 1], a[0], a[1], a[2], a[3], wl[rg][0] & mask, wl[rg][1] & mask);
                }
            }
            float d[4];
#pragma unroll
            for (int b = 0; b < 4; b++)
                d[b] = ((acc[0][b] + acc[1][b]) + (acc[2][b] + acc[3][b])) + ((acc[4][b] + acc[5][b]) + (acc[6][b] + acc[7][b]));
            pv0 = d[0] + __shfl_xor_sync(0xffffffffu, d[2], 2);
            pv1 = d[1] + __shfl_xor_sync(0xffffffffu, d[3], 2);
            pbh = (t / TPB) & (BH - 1);
            asm volatile("atom.relaxed.gpu.global.add.v4.f32 {%0,%1,%2,%3}, [%4], {%5,%6,%7,%8};"
                         : "=f"(pr0), "=f"(pr1), "=f"(pr2), "=f"(prn)
                         : "l"(oword(pbh, threadIdx.x)), "f"(pv0), "f"(pv1), "f"(0.f), "f"(1.0f) : "memory");
            __syncwarp();
            if (lane == 0) mbar_arrive(smem_u32(&bars.empty[slot]));
        }
        settle();
    }
}

typedef CUresult (*EncodeFn)(CUtensorMap*, CUtensorMapDataType, cuuint32_t, void*, const cuuint64_t*, const cuuint64_t*,
                             const cuuint32_t*, const cuuint32_t*, CUtensorMapInterleave, CUtensorMapSwizzle,
                             CUtensorMapL2promotion, CUtensorMapFloatOOBfill);

void make_proj_map(EncodeFn enc, CUtensorMap* m, const void* base) {
    cuuint64_t dims[2] = {(cuuint64_t)SKV, (cuuint64_t)RK};
    cuuint64_t strides[1] = {(cuuint64_t)SKV * 2};
    cuuint32_t box[2] = {(cuuint32_t)TROWS, (cuuint32_t)RK};
    cuuint32_t es[2] = {1, 1};
    enc(m, CU_TENSOR_MAP_DATA_TYPE_BFLOAT16, 2, const_cast<void*>(base), dims, strides, box, es,
        CU_TENSOR_MAP_INTERLEAVE_NONE, CU_TENSOR_MAP_SWIZZLE_128B, CU_TENSOR_MAP_L2_PROMOTION_NONE,
        CU_TENSOR_MAP_FLOAT_OOB_FILL_NONE);
}

}

extern "C" void kernel_launch(void* const* d_in, const int* in_sizes, int n_in, void* d_out, int out_size) {
    (void)in_sizes; (void)n_in; (void)out_size;
    static EncodeFn enc = nullptr;
    static int grid = 0;
    if (!enc) {
        void* fn = nullptr;
        cudaDriverEntryPointQueryResult st;
        cudaGetDriverEntryPoint("cuTensorMapEncodeTiled", &fn, cudaEnableDefault, &st);
        enc = (EncodeFn)fn;
        cudaFuncSetAttribute(linformer_decode_kernel, cudaFuncAttributeMaxDynamicSharedMemorySize, SMEM_BYTES);
        int dev = 0, sms = 0, occ = 0;
        cudaGetDevice(&dev);
        cudaDeviceGetAttribute(&sms, cudaDevAttrMultiProcessorCount, dev);
        cudaOccupancyMaxActiveBlocksPerMultiprocessor(&occ, linformer_decode_kernel, NTHREADS, SMEM_BYTES);
        if (occ > 2) occ = 2;
        grid = sms * occ;
    }
    CUtensorMap mapE, mapF;
    make_proj_map(enc, &mapE, d_in[3]);
    make_proj_map(enc, &mapF, d_in[4]);
    linformer_decode_kernel<<<grid, NTHREADS, SMEM_BYTES>>>(
        mapE, mapF, (const __nv_bfloat16*)d_in[0], (const __nv_bfloat16*)d_in[1], (const __nv_bfloat16*)d_in[2],
        (__nv_bfloat16*)d_out);
}
```

```cpp
#include <cuda_runtime.h>
#include <cuda_bf16.h>
#include <cuda.h>
#include <stdint.h>

namespace {

constexpr int BH = 64;
constexpr int SKV = 8192;
constexpr int DH = 256;
constexpr int RK = 64;
constexpr int TROWS = 64;
constexpr int TPB = SKV / TROWS;
constexpr uint32_t KTILES = BH * TPB;
constexpr uint32_t NTILES = 2 * KTILES;
constexpr int FCH = 4;
constexpr int VPB = TPB - FCH;
constexpr uint32_t TK_WJ = KTILES + 16 * VPB;
constexpr uint32_t TK_FIN = KTILES + BH * VPB + FCH;
constexpr uint32_t NTICKETS = TK_FIN + BH * 4;
constexpr uint32_t T_WJOB = 0x10000u, T_FIN = 0x20000u, T_END = 0xffffffffu;
constexpr uint32_t MAIN_BYTES = TROWS * DH * 2;
constexpr uint32_t EF_BYTES = RK * TROWS * 2;
constexpr uint32_t SLOT_BYTES = 41984;
constexpr int FD = 4;
constexpr uint32_t SMEM_BYTES = 2 * SLOT_BYTES + FD * 1024 + 1024;
constexpr int NTHREADS = 192;
constexpr int REPK = 2;
constexpr int LSTR = 288;
constexpr uint32_t STOP_TK = NTICKETS - 750;
constexpr int GAP_CLK = 300;
constexpr int SPIN_LIMIT = 1 << 22;

__device__ __align__(4096) unsigned int g_ticket[1024];
__device__ __align__(4096) unsigned long long g_ready[512];
__device__ __align__(4096) float g_sacc[BH * (3 * REPK + 1) * LSTR];
__device__ __align__(4096) float g_oacc[BH * 16 * LSTR];
__device__ __align__(4096) uint32_t g_w[BH * 64 * FCH];
__device__ __align__(4096) uint32_t g_p[BH * 64];

__device__ __forceinline__ float* oword(uint32_t bh, uint32_t w) { return g_oacc + (bh * 16 + (w >> 3)) * LSTR + (w & 7) * 4; }
__device__ __forceinline__ float* sline(uint32_t bh, uint32_t i) { return g_sacc + (bh * (3 * REPK + 1) + i) * LSTR; }

__device__ __forceinline__ uint32_t smem_u32(const void* p) { return (uint32_t)__cvta_generic_to_shared(p); }
__device__ __forceinline__ void mbar_init(uint32_t bar, uint32_t cnt) {
    asm volatile("mbarrier.init.shared::cta.b64 [%0], %1;" ::"r"(bar), "r"(cnt) : "memory");
}
__device__ __forceinline__ void mbar_expect(uint32_t bar, uint32_t bytes) {
    asm volatile("mbarrier.arrive.expect_tx.shared::cta.b64 _, [%0], %1;" ::"r"(bar), "r"(bytes) : "memory");
}
__device__ __forceinline__ void mbar_arrive(uint32_t bar) {
    asm volatile("mbarrier.arrive.shared::cta.b64 _, [%0];" ::"r"(bar) : "memory");
}
__device__ __forceinline__ bool mbar_try(uint32_t bar, uint32_t parity) {
    uint32_t ok;
    asm volatile("{\n.reg .pred p;\nmbarrier.try_wait.parity.shared::cta.b64 p, [%1], %2;\nselp.u32 %0, 1, 0, p;\n}"
                 : "=r"(ok) : "r"(bar), "r"(parity) : "memory");
    return ok;
}
__device__ __forceinline__ bool mbar_test(uint32_t bar, uint32_t parity) {
    uint32_t ok;
    asm volatile("{\n.reg .pred p;\nmbarrier.test_wait.parity.shared::cta.b64 p, [%1], %2;\nselp.u32 %0, 1, 0, p;\n}"
                 : "=r"(ok) : "r"(bar), "r"(parity) : "memory");
    return ok;
}
__device__ __forceinline__ void mbar_wait(uint32_t bar, uint32_t parity) {
#pragma unroll 1
    for (int i = 0; i < SPIN_LIMIT; i++)
        if (mbar_try(bar, parity)) return;
    __trap();
}
__device__ __forceinline__ void bulk_load(uint32_t dst, const void* src, uint32_t bytes, uint32_t bar) {
    asm volatile("cp.async.bulk.shared::cluster.global.mbarrier::complete_tx::bytes [%0], [%1], %2, [%3];"
                 ::"r"(dst), "l"(src), "r"(bytes), "r"(bar) : "memory");
}
__device__ __forceinline__ void bulk_load_hint(uint32_t dst, const void* src, uint32_t bytes, uint32_t bar, uint64_t pol) {
    asm volatile("cp.async.bulk.shared::cluster.global.mbarrier::complete_tx::bytes.L2::cache_hint [%0], [%1], %2, [%3], %4;"
                 ::"r"(dst), "l"(src), "r"(bytes), "r"(bar), "l"(pol) : "memory");
}
__device__ __forceinline__ void tma_load_2d(uint32_t dst, const CUtensorMap* map, int c0, int c1, uint32_t bar) {
    asm volatile("cp.async.bulk.tensor.2d.shared::cluster.global.mbarrier::complete_tx::bytes [%0], [%1, {%3, %4}], [%2];"
                 ::"r"(dst), "l"(map), "r"(bar), "r"(c0), "r"(c1) : "memory");
}
__device__ __forceinline__ void tma_load_2d_hint(uint32_t dst, const CUtensorMap* map, int c0, int c1, uint32_t bar, uint64_t pol) {
    asm volatile("cp.async.bulk.tensor.2d.shared::cluster.global.mbarrier::complete_tx::bytes.L2::cache_hint [%0], [%1, {%3, %4}], [%2], %5;"
                 ::"r"(dst), "l"(map), "r"(bar), "r"(c0), "r"(c1), "l"(pol) : "memory");
}
__device__ __forceinline__ void ldsm4(uint32_t (&r)[4], uint32_t addr) {
    asm volatile("ldmatrix.sync.aligned.m8n8.x4.shared.b16 {%0,%1,%2,%3}, [%4];"
                 : "=r"(r[0]), "=r"(r[1]), "=r"(r[2]), "=r"(r[3]) : "r"(addr) : "memory");
}
__device__ __forceinline__ void ldsm4t(uint32_t (&r)[4], uint32_t addr) {
    asm volatile("ldmatrix.sync.aligned.m8n8.x4.trans.shared.b16 {%0,%1,%2,%3}, [%4];"
                 : "=r"(r[0]), "=r"(r[1]), "=r"(r[2]), "=r"(r[3]) : "r"(addr) : "memory");
}
__device__ __forceinline__ void lds4(uint32_t& a, uint32_t& b, uint32_t& c, uint32_t& d, uint32_t addr) {
    asm volatile("ld.shared.v4.u32 {%0,%1,%2,%3}, [%4];" : "=r"(a), "=r"(b), "=r"(c), "=r"(d) : "r"(addr) : "memory");
}
__device__ __forceinline__ void lds2f(float& a, float& b, uint32_t addr) {
    asm volatile("ld.shared.v2.f32 {%0,%1}, [%2];" : "=f"(a), "=f"(b) : "r"(addr) : "memory");
}
__device__ __forceinline__ void mma16816(float (&d)[4], uint32_t a0, uint32_t a1, uint32_t a2, uint32_t a3,
                                         uint32_t b0, uint32_t b1) {
    asm volatile("mma.sync.aligned.m16n8k16.row.col.f32.bf16.bf16.f32 {%0,%1,%2,%3}, {%4,%5,%6,%7}, {%8,%9}, {%0,%1,%2,%3};"
                 : "+f"(d[0]), "+f"(d[1]), "+f"(d[2]), "+f"(d[3])
                 : "r"(a0), "r"(a1), "r"(a2), "r"(a3), "r"(b0), "r"(b1));
}
__device__ __forceinline__ void split_bf16x2(float x0, float x1, uint32_t& hi, uint32_t& lo) {
    asm("cvt.rn.bf16x2.f32 %0, %1, %2;" : "=r"(hi) : "f"(x1), "f"(x0));
    float r0 = x0 - __uint_as_float(hi << 16);
    float r1 = x1 - __uint_as_float(hi & 0xffff0000u);
    asm("cvt.rn.bf16x2.f32 %0, %1, %2;" : "=r"(lo) : "f"(r1), "f"(r0));
}
__device__ __forceinline__ bool arrive_n(float* p, uint32_t n) {
    uint32_t old;
    asm volatile("atom.relaxed.gpu.global.inc.u32 %0, [%1], %2;" : "=r"(old) : "l"(p), "r"(n - 1) : "memory");
    return old == n - 1;
}
__device__ __forceinline__ void ld_word(float (&t)[4], const float* p) {
    asm volatile("ld.relaxed.gpu.global.v4.f32 {%0,%1,%2,%3}, [%4];" : "=f"(t[0]), "=f"(t[1]), "=f"(t[2]), "=f"(t[3]) : "l"(p) : "memory");
}
__device__ __forceinline__ uint32_t ld_acquire(const void* p) {
    uint32_t v;
    asm volatile("ld.acquire.gpu.global.u32 %0, [%1];" : "=r"(v) : "l"(p) : "memory");
    return v;
}
__device__ __forceinline__ void fence_async_global() { asm volatile("fence.proxy.async.global;" ::: "memory"); }
__device__ __forceinline__ void fence_gpu() { asm volatile("fence.acq_rel.gpu;" ::: "memory"); }

__device__ __forceinline__ uint32_t item_of(uint32_t tk) {
    if (tk < KTILES) return tk;
    if (tk >= TK_FIN) return T_FIN | (tk - TK_FIN);
    if (tk >= TK_WJ) {
        if (tk < TK_WJ + FCH) return T_WJOB | (tk - TK_WJ);
        tk -= FCH;
    }
    const uint32_t r = tk - KTILES;
    return KTILES + (r / VPB) * TPB + r % VPB;
}

struct Bars {
    unsigned long long fullA[2], fullB[2], empty[2], ffull[FD], fempty[FD];
    uint32_t item[2];
    uint32_t fkey[FD];
};

__device__ __forceinline__ void softmax_head(uint32_t bh, int lane) {
    const float sc = 0.0625f * 1.4426950408889634f;
    unsigned long long raw[REPK];
#pragma unroll
    for (int i = 0; i < REPK; i++)
        asm volatile("atom.relaxed.gpu.global.exch.b64 %0, [%1], 0;" : "=l"(raw[i])
                     : "l"(sline(bh, 3 * i + (lane >> 4)) + (lane & 15) * 2) : "memory");
    float a = 0.f, b = 0.f;
#pragma unroll
    for (int i = 0; i < REPK; i++) { a += __uint_as_float((uint32_t)raw[i]); b += __uint_as_float((uint32_t)(raw[i] >> 32)); }
    a *= sc; b *= sc;
    float m = fmaxf(a, b);
#pragma unroll
    for (int o = 16; o > 0; o >>= 1) m = fmaxf(m, __shfl_xor_sync(0xffffffffu, m, o));
    const float p0 = exp2f(a - m), p1 = exp2f(b - m);
    float sum = p0 + p1;
#pragma unroll
    for (int o = 16; o > 0; o >>= 1) sum += __shfl_xor_sync(0xffffffffu, sum, o);
    const float inv = 1.0f / sum;
    uint32_t hi, lo;
    split_bf16x2(p0 * inv, p1 * inv, hi, lo);
    *reinterpret_cast<uint2*>(g_p + bh * 64 + (lane >> 3) * 16 + (lane & 3) * 4 + ((lane >> 2) & 1) * 2) = make_uint2(hi, lo);
#pragma unroll
    for (int i = 0; i < 4; i++) *reinterpret_cast<float4*>(oword(bh, i * 32 + lane)) = make_float4(0.f, 0.f, 0.f, 0.f);
}

__global__ void __launch_bounds__(NTHREADS, 2)
linformer_decode_kernel(const __grid_constant__ CUtensorMap mapE, const __grid_constant__ CUtensorMap mapF,
                        const __grid_constant__ CUtensorMap mapV,
                        const __nv_bfloat16* __restrict__ q, const __nv_bfloat16* __restrict__ k,
                        const __nv_bfloat16* __restrict__ v, __nv_bfloat16* __restrict__ out, uint32_t nlast) {
    extern __shared__ unsigned char smem_raw[];
    __shared__ __align__(16) Bars bars;
    const uint32_t sbase = (smem_u32(smem_raw) + 1023u) & ~1023u;
    const uint32_t fbase = sbase + 2 * SLOT_BYTES;
    const int warp = threadIdx.x >> 5, lane = threadIdx.x & 31;
    const uint32_t G = gridDim.x;

    uint64_t pol;
    asm volatile("createpolicy.fractional.L2::evict_first.b64 %0, 1.0;" : "=l"(pol));
    auto issue_aux = [&](uint32_t t, int slot) {
        const uint32_t ph = t >= KTILES;
        const uint32_t bh = (t / TPB) & (BH - 1), j = t % TPB;
        const uint32_t dst = sbase + slot * SLOT_BYTES;
        const uint32_t bB = smem_u32(&bars.fullB[slot]);
        bars.item[slot] = t;
        mbar_expect(bB, EF_BYTES + (ph ? 256u : 512u));
        tma_load_2d(dst + MAIN_BYTES, ph ? &mapF : &mapE, j * TROWS, 0, bB);
        if (ph) bulk_load(dst + MAIN_BYTES + EF_BYTES, g_p + bh * 64, 256, bB);
        else    bulk_load(dst + MAIN_BYTES + EF_BYTES, q + bh * DH, 512, bB);
    };

    if (threadIdx.x == 128) {
        for (int s = 0; s < 2; s++) {
            mbar_init(smem_u32(&bars.fullA[s]), 1);
            mbar_init(smem_u32(&bars.fullB[s]), 1);
            mbar_init(smem_u32(&bars.empty[s]), 4);
        }
        for (int s = 0; s < FD; s++) {
            mbar_init(smem_u32(&bars.ffull[s]), 4);
            mbar_init(smem_u32(&bars.fempty[s]), 1);
        }
        asm volatile("fence.proxy.async.shared::cta;" ::: "memory");
        mbar_expect(smem_u32(&bars.fullA[0]), MAIN_BYTES);
        bulk_load_hint(sbase, k + (size_t)blockIdx.x * (TROWS * DH), MAIN_BYTES, smem_u32(&bars.fullA[0]), pol);
        issue_aux(blockIdx.x, 0);
    }
    __syncthreads();

    if (warp == 4) {
        if (lane == 0) {
            unsigned long long ready = 0;
            bool wok = false;
            uint32_t parity = 2;
            uint32_t tk = G + blockIdx.x;
            for (uint32_t it = 0;; it++) {
                const int slot = (it + 1) & 1;
                if (it >= 1) mbar_wait(smem_u32(&bars.empty[slot]), ((it - 1) >> 1) & 1);
                if (tk >= NTICKETS) {
                    if (tk == G + NTICKETS - 1) *reinterpret_cast<volatile uint32_t*>(&g_ticket[8]) = parity ^ 1;
                    bars.item[slot] = T_END;
                    mbar_arrive(smem_u32(&bars.fullB[slot]));
                    break;
                }
                const uint32_t cur = item_of(tk);
                const uint32_t dst = sbase + slot * SLOT_BYTES;
                const uint32_t bA = smem_u32(&bars.fullA[slot]), bB = smem_u32(&bars.fullB[slot]);
                const uint32_t prevA = smem_u32(&bars.fullA[it & 1]), prevP = (it >> 1) & 1;
                if (cur >= KTILES && !(cur & T_FIN)) {
                    const unsigned long long need = (cur & T_WJOB) ? ~0ull : 1ull << ((cur / TPB) & (BH - 1));
                    if ((ready & need) != need) {
                        int i = 0;
                        do {
                            asm volatile("ld.acquire.gpu.global.u64 %0, [%1];" : "=l"(ready) : "l"(&g_ready[0]) : "memory");
                            ready ^= parity ? ~0ull : 0ull;
                            if (++i > SPIN_LIMIT) __trap();
                        } while ((ready & need) != need);
                        fence_async_global();
                        asm volatile("prefetch.tensormap [%0];" ::"l"(&mapV) : "memory");
                    }
                }
                if (!wok && tk > TK_WJ + 3000) {
                    int i = 0;
                    do {
                        wok = ld_acquire(&g_ready[16]) == (parity ? 0u : 4u * FCH);
                        if (++i > SPIN_LIMIT) __trap();
                    } while (!wok && (cur & T_FIN));
                    if (wok) fence_async_global();
                }
                if (cur < NTILES) {
                    issue_aux(cur, slot);
                    mbar_expect(bA, MAIN_BYTES);
                    const __nv_bfloat16* src = (cur >= KTILES ? v : k) + (size_t)(cur & (KTILES - 1)) * (TROWS * DH);
                    mbar_wait(prevA, prevP);
                    if (tk >= 1000u && tk < STOP_TK - 200u) {
                        const long long c0 = clock64();
                        while (clock64() - c0 < GAP_CLK) {}
                    }
                    bulk_load_hint(dst, src, MAIN_BYTES, bA, pol);
                } else if (cur & T_FIN) {
                    const uint32_t h = (cur & 255u) >> 2;
                    bars.item[slot] = cur;
                    mbar_expect(bB, FCH * 256);
                    bulk_load(dst + MAIN_BYTES, g_w + h * (64 * FCH), FCH * 256, bB);
                    mbar_expect(bA, MAIN_BYTES);
                    mbar_wait(prevA, prevP);
                    tma_load_2d_hint(dst, &mapV, (cur & 3u) * 64, h * SKV + VPB * TROWS, bA, pol);
                } else {
                    bars.item[slot] = cur;
                    mbar_expect(bB, EF_BYTES);
                    tma_load_2d(dst + MAIN_BYTES, &mapF, (VPB + (cur & 3u)) * TROWS, 0, bB);
                    mbar_expect(bA, BH * 256);
                    bulk_load(dst, g_p, BH * 256, bA);
                }
                if (it == 0) asm volatile("ld.relaxed.gpu.global.u32 %0, [%1];" : "=r"(parity) : "l"(&g_ticket[8]) : "memory");
                if (it == 1 && parity > 1) __trap();
                if (blockIdx.x >= nlast && tk >= STOP_TK) {
                    uint32_t raw;
                    int i = 0;
                    do {
                        __nanosleep(300);
                        asm volatile("ld.relaxed.gpu.global.u32 %0, [%1];" : "=r"(raw) : "l"(&g_ticket[0]) : "memory");
                        if (++i > SPIN_LIMIT) __trap();
                    } while (raw < NTICKETS - 2 * G);
                }
                tk = 2 * G + atomicInc(&g_ticket[0], NTICKETS - G - 1);
            }
        }
    } else if (warp == 5) {
        for (uint32_t e = 0;; e++) {
            mbar_wait(smem_u32(&bars.ffull[e % FD]), (e / FD) & 1);
            const uint32_t tl = bars.fkey[e % FD];
            if (tl == T_END) break;
            const uint32_t bh = tl / TPB, rep = tl % REPK;
            const uint32_t fb = fbase + (e % FD) * 1024;
            float sx = 0.f, sy = 0.f;
#pragma unroll
            for (int w = 0; w < 4; w++) {
                float x, y;
                lds2f(x, y, fb + w * 256 + lane * 8);
                sx += x; sy += y;
            }
            float r0, r1;
            asm volatile("atom.relaxed.gpu.global.add.v2.f32 {%0,%1}, [%2], {%3,%4};" : "=f"(r0), "=f"(r1)
                         : "l"(sline(bh, 3 * rep + (lane >> 4)) + (lane & 15) * 2), "f"(sx), "f"(sy) : "memory");
            __syncwarp();
            if (lane == 0) mbar_arrive(smem_u32(&bars.fempty[e % FD]));
            if (__ballot_sync(0xffffffffu, (__float_as_uint(r0) ^ __float_as_uint(r1)) == 0x7fb5a3c1u) == 0x5a5a5a5au) __nanosleep(1);
            uint32_t last = 0;
            if (lane == 0 && arrive_n(sline(bh, 3 * rep + 2), TPB / REPK)) last = arrive_n(sline(bh, 3 * REPK), REPK);
            if (__shfl_sync(0xffffffffu, last, 0)) {
                softmax_head(bh, lane);
                fence_async_global();
                fence_gpu();
                __syncwarp();
                if (lane == 0) atomicXor(&g_ready[0], 1ull << bh);
            }
        }
    } else {
        const int mi = lane >> 3, ri = lane & 7, g = lane >> 2, m = lane & 3;
        const uint32_t e_off = MAIN_BYTES + ((mi & 1) * 8 + ri) * 128 + (((2 * warp + (mi >> 1)) ^ ri) << 4);
        const uint32_t f_off = MAIN_BYTES + ((mi & 1) * 8 + ri) * 128 + (((mi >> 1) ^ ri) << 4);
        const uint32_t k_off = (warp * 16 + (mi & 1) * 8 + ri) * 512 + (mi >> 1) * 128 + ri * 16;
        const uint32_t v_off = ((mi >> 1) * 8 + ri) * 512 + warp * 128 + ((ri ^ ((mi & 1) * 4)) << 4);
        const uint32_t vf_off = ((mi >> 1) * 8 + ri) * 128 + (((2 * warp + (mi & 1)) ^ ri) << 4);
        const uint32_t q_off = MAIN_BYTES + EF_BYTES + mi * 128 + ri * 16;
        const int t0 = g ^ (2 * m);
        uint32_t fi = 0;
        bool kdone = false;
        for (uint32_t it = 0;; it++) {
            const int slot = it & 1;
            const uint32_t par = (it >> 1) & 1;
            const uint32_t sb = sbase + slot * SLOT_BYTES;
            mbar_wait(smem_u32(&bars.fullB[slot]), par);
            const uint32_t t = bars.item[slot];
            if (t < KTILES) {
                uint32_t qf[8][4];
#pragma unroll
                for (int tt = 0; tt < 8; tt++) ldsm4(qf[tt], (sb + q_off) ^ (tt << 4));
                float acc[4][4];
#pragma unroll
                for (int a = 0; a < 4; a++)
#pragma unroll
                    for (int b = 0; b < 4; b++) acc[a][b] = 0.f;
                mbar_wait(smem_u32(&bars.fullA[slot]), par);
#pragma unroll
                for (int tt = 0; tt < 8; tt++) {
                    const uint32_t addr = (sb + k_off) ^ (tt << 4);
#pragma unroll
                    for (int gp = 0; gp < 2; gp++) {
                        uint32_t a[4];
                        ldsm4(a, addr + gp * 256);
                        mma16816(acc[gp * 2 + (tt & 1)], a[0], a[1], a[2], a[3], qf[tt][gp * 2], qf[tt][gp * 2 + 1]);
                    }
                }
                uint32_t ea[4][4];
#pragma unroll
                for (int mt = 0; mt < 4; mt++) ldsm4(ea[mt], sb + e_off + mt * 2048);
                __syncwarp();
                if (lane == 0) mbar_arrive(smem_u32(&bars.empty[slot]));
                float vlo = 0.f, vhi = 0.f;
#pragma unroll
                for (int a = 0; a < 4; a++) {
                    vlo += (g & 1) ? acc[a][1] : acc[a][0];
                    vhi += (g & 1) ? acc[a][3] : acc[a][2];
                }
                const float x0 = __shfl_sync(0xffffffffu, vlo, 9 * m), x1 = __shfl_sync(0xffffffffu, vlo, 9 * m + 4);
                const float x2 = __shfl_sync(0xffffffffu, vhi, 9 * m), x3 = __shfl_sync(0xffffffffu, vhi, 9 * m + 4);
                uint32_t h0, l0, h1, l1;
                split_bf16x2(x0, x1, h0, l0);
                split_bf16x2(x2, x3, h1, l1);
                const uint32_t b0 = g == 0 ? h0 : (g == 1 ? l0 : 0u);
                const uint32_t b1 = g == 0 ? h1 : (g == 1 ? l1 : 0u);
                float sc[4][4];
#pragma unroll
                for (int mt = 0; mt < 4; mt++) {
#pragma unroll
                    for (int b = 0; b < 4; b++) sc[mt][b] = 0.f;
                    mma16816(sc[mt], ea[mt][0], ea[mt][1], ea[mt][2], ea[mt][3], b0, b1);
                }
                const uint32_t fb = fbase + (fi % FD) * 1024;
                mbar_wait(smem_u32(&bars.fempty[fi % FD]), ((fi / FD) & 1) ^ 1);
                if (m == 0) {
#pragma unroll
                    for (int mt = 0; mt < 4; mt++) {
                        asm volatile("st.shared.f32 [%0], %1;" ::"r"(fb + warp * 256 + (mt * 16 + g) * 4), "f"(sc[mt][0] + sc[mt][1]) : "memory");
                        asm volatile("st.shared.f32 [%0], %1;" ::"r"(fb + warp * 256 + (mt * 16 + g + 8) * 4), "f"(sc[mt][2] + sc[mt][3]) : "memory");
                    }
                }
                if (threadIdx.x == 0) bars.fkey[fi % FD] = t;
                __syncwarp();
                if (lane == 0) mbar_arrive(smem_u32(&bars.ffull[fi % FD]));
                fi++;
                continue;
            }
            if (!kdone) {
                mbar_wait(smem_u32(&bars.fempty[fi % FD]), ((fi / FD) & 1) ^ 1);
                if (threadIdx.x == 0) bars.fkey[fi % FD] = T_END;
                __syncwarp();
                if (lane == 0) mbar_arrive(smem_u32(&bars.ffull[fi % FD]));
                kdone = true;
            }
            if (t == T_END) break;
            if (t & T_WJOB) {
                float wacc[8][4];
#pragma unroll
                for (int a = 0; a < 8; a++)
#pragma unroll
                    for (int b = 0; b < 4; b++) wacc[a][b] = 0.f;
                mbar_wait(smem_u32(&bars.fullA[slot]), par);
#pragma unroll 1
                for (int ks = 0; ks < 4; ks++) {
                    uint32_t x[4], y[4];
                    const uint32_t pa = sb + (warp * 16 + g) * 256 + ks * 64 + m * 16;
                    lds4(x[0], x[1], x[2], x[3], pa);
                    lds4(y[0], y[1], y[2], y[3], pa + 2048);
#pragma unroll
                    for (int rg = 0; rg < 4; rg++) {
                        uint32_t fq[4];
                        ldsm4t(fq, ((sb + f_off) ^ (rg << 5)) + ks * 2048);
                        mma16816(wacc[2 * rg], x[0], y[0], x[2], y[2], fq[0], fq[1]);
                        mma16816(wacc[2 * rg + 1], x[0], y[0], x[2], y[2], fq[2], fq[3]);
                        mma16816(wacc[2 * rg], x[1], y[1], x[3], y[3], fq[0], fq[1]);
                        mma16816(wacc[2 * rg + 1], x[1], y[1], x[3], y[3], fq[2], fq[3]);
                    }
                }
                __syncwarp();
                if (lane == 0) mbar_arrive(smem_u32(&bars.empty[slot]));
                uint32_t* dst = g_w + (warp * 16 + g) * (64 * FCH) + (t & 3u) * 64 + m * 4;
#pragma unroll
                for (int rg = 0; rg < 4; rg++)
#pragma unroll
                    for (int hh = 0; hh < 2; hh++) {
                        uint4 o;
                        split_bf16x2(wacc[2 * rg][2 * hh], wacc[2 * rg][2 * hh + 1], o.x, o.z);
                        split_bf16x2(wacc[2 * rg + 1][2 * hh], wacc[2 * rg + 1][2 * hh + 1], o.y, o.w);
                        *reinterpret_cast<uint4*>(dst + hh * 8 * (64 * FCH) + rg * 16) = o;
                    }
                fence_async_global();
                fence_gpu();
                __syncwarp();
                if (lane == 0) atomicInc(reinterpret_cast<unsigned int*>(&g_ready[16]), 8 * FCH - 1);
                continue;
            }
            if (t & T_FIN) {
                const uint32_t bh = (t & 255u) >> 2;
                const float* word = oword(bh, (t & 3u) * 32 + g * 4 + warp);
                uint32_t fb0[4 * FCH], fb1[4 * FCH];
#pragma unroll
                for (int rg = 0; rg < 4 * FCH; rg++) {
                    uint32_t h0, h1, l0, l1;
                    lds4(h0, h1, l0, l1, sb + MAIN_BYTES + rg * 64 + m * 16);
                    fb0[rg] = g == 0 ? h0 : (g == 1 ? l0 : 0u);
                    fb1[rg] = g == 0 ? h1 : (g == 1 ? l1 : 0u);
                    asm volatile("" : "+r"(fb0[rg]), "+r"(fb1[rg]));
                }
                float tot[4] = {0.f, 0.f, 0.f, 0.f};
                if (m == 0) ld_word(tot, word);
                float acc[4][4];
#pragma unroll
                for (int a = 0; a < 4; a++)
#pragma unroll
                    for (int b = 0; b < 4; b++) acc[a][b] = 0.f;
                mbar_wait(smem_u32(&bars.fullA[slot]), par);
                const bool nxt_ok = mbar_test(smem_u32(&bars.fullB[slot ^ 1]), ((it + 1) >> 1) & 1);
                const uint32_t nxt = *reinterpret_cast<volatile uint32_t*>(&bars.item[slot ^ 1]);
#pragma unroll
                for (int rg = 0; rg < 4 * FCH; rg++) {
                    uint32_t a[4];
                    ldsm4t(a, sb + vf_off + rg * 2048);
                    mma16816(acc[rg & 3], a[0], a[1], a[2], a[3], fb0[rg], fb1[rg]);
                }
                __syncwarp();
                if (lane == 0) mbar_arrive(smem_u32(&bars.empty[slot]));
                if (m == 0) {
                    float s0 = 0.f, s1 = 0.f;
#pragma unroll
                    for (int a = 0; a < 4; a++) { s0 += acc[a][0] + acc[a][1]; s1 += acc[a][2] + acc[a][3]; }
                    int i = 0;
                    while (tot[3] != (float)VPB) {
                        ld_word(tot, word);
                        if (++i > SPIN_LIMIT) __trap();
                    }
                    __nv_bfloat16* o = out + bh * DH + (t & 3u) * 64 + warp * 16 + g;
                    o[0] = __float2bfloat16(s0 + tot[0]);
                    o[8] = __float2bfloat16(s1 + tot[1]);
                }
                if (nxt_ok && nxt == T_END) asm volatile("exit;");
                __syncwarp();
                continue;
            }
            uint32_t wh[4][2], wl[4][2];
            {
                float wacc[8][4];
#pragma unroll
                for (int a = 0; a < 8; a++)
#pragma unroll
                    for (int b = 0; b < 4; b++) wacc[a][b] = 0.f;
#pragma unroll
                for (int ks = 0; ks < 4; ks++) {
                    uint32_t pa[4];
                    lds4(pa[0], pa[1], pa[2], pa[3], sb + MAIN_BYTES + EF_BYTES + ks * 64 + m * 16);
#pragma unroll
                    for (int rg = 0; rg < 4; rg++) {
                        uint32_t fq[4];
                        ldsm4t(fq, ((sb + f_off) ^ (rg << 5)) + ks * 2048);
                        mma16816(wacc[2 * rg], pa[0], pa[1], pa[2], pa[3], fq[0], fq[1]);
                        mma16816(wacc[2 * rg + 1], pa[0], pa[1], pa[2], pa[3], fq[2], fq[3]);
                    }
                }
#pragma unroll
                for (int rg = 0; rg < 4; rg++)
#pragma unroll
                    for (int h = 0; h < 2; h++)
                        split_bf16x2(wacc[2 * rg + h][0] + wacc[2 * rg + h][2], wacc[2 * rg + h][1] + wacc[2 * rg + h][3],
                                     wh[rg][h], wl[rg][h]);
            }
            float acc[8][4];
#pragma unroll
            for (int a = 0; a < 8; a++)
#pragma unroll
                for (int b = 0; b < 4; b++) acc[a][b] = 0.f;
            mbar_wait(smem_u32(&bars.fullA[slot]), par);
#pragma unroll
            for (int rg = 0; rg < 4; rg++) {
#pragma unroll
                for (int tt = 0; tt < 4; tt++) {
                    const uint32_t mask = (tt == t0 ? 0x0000ffffu : 0u) | (tt == (t0 ^ 1) ? 0xffff0000u : 0u);
                    uint32_t a[4];
                    ldsm4t(a, ((sb + v_off) ^ (tt << 4)) + rg * 8192);
                    mma16816(acc[tt * 2], a[0], a[1], a[2], a[3], wh[rg][0] & mask, wh[rg][1] & mask);
                    mma16816(acc[tt * 2 + 1], a[0], a[1], a[2], a[3], wl[rg][0] & mask, wl[rg][1] & mask);
                }
            }
            __syncwarp();
            if (lane == 0) mbar_arrive(smem_u32(&bars.empty[slot]));
            float d[4];
#pragma unroll
            for (int b = 0; b < 4; b++)
                d[b] = ((acc[0][b] + acc[1][b]) + (acc[2][b] + acc[3][b])) + ((acc[4][b] + acc[5][b]) + (acc[6][b] + acc[7][b]));
            const float pv0 = d[0] + __shfl_xor_sync(0xffffffffu, d[2], 2);
            const float pv1 = d[1] + __shfl_xor_sync(0xffffffffu, d[3], 2);
            asm volatile("red.relaxed.gpu.global.add.v4.f32 [%0], {%1,%2,%3,%4};"
                         ::"l"(oword((t / TPB) & (BH - 1), threadIdx.x)), "f"(pv0), "f"(pv1), "f"(0.f), "f"(1.0f) : "memory");
        }
    }
}

typedef CUresult (*EncodeFn)(CUtensorMap*, CUtensorMapDataType, cuuint32_t, void*, const cuuint64_t*, const cuuint64_t*,
                             const cuuint32_t*, const cuuint32_t*, CUtensorMapInterleave, CUtensorMapSwizzle,
                             CUtensorMapL2promotion, CUtensorMapFloatOOBfill);

void make_map(EncodeFn enc, CUtensorMap* m, const void* base, uint64_t cols, uint64_t rows, uint32_t box_rows) {
    cuuint64_t dims[2] = {cols, rows};
    cuuint64_t strides[1] = {cols * 2};
    cuuint32_t box[2] = {64, box_rows};
    cuuint32_t es[2] = {1, 1};
    enc(m, CU_TENSOR_MAP_DATA_TYPE_BFLOAT16, 2, const_cast<void*>(base), dims, strides, box, es,
        CU_TENSOR_MAP_INTERLEAVE_NONE, CU_TENSOR_MAP_SWIZZLE_128B, CU_TENSOR_MAP_L2_PROMOTION_NONE,
        CU_TENSOR_MAP_FLOAT_OOB_FILL_NONE);
}

}

extern "C" void kernel_launch(void* const* d_in, const int* in_sizes, int n_in, void* d_out, int out_size) {
    (void)in_sizes; (void)n_in; (void)out_size;
    static EncodeFn enc = nullptr;
    static int grid = 0, sms = 0;
    if (!enc) {
        void* fn = nullptr;
        cudaDriverEntryPointQueryResult st;
        cudaGetDriverEntryPoint("cuTensorMapEncodeTiled", &fn, cudaEnableDefault, &st);
        enc = (EncodeFn)fn;
        cudaFuncSetAttribute(linformer_decode_kernel, cudaFuncAttributeMaxDynamicSharedMemorySize, SMEM_BYTES);
        int dev = 0, occ = 0;
        cudaGetDevice(&dev);
        cudaDeviceGetAttribute(&sms, cudaDevAttrMultiProcessorCount, dev);
        cudaOccupancyMaxActiveBlocksPerMultiprocessor(&occ, linformer_decode_kernel, NTHREADS, SMEM_BYTES);
        grid = sms * (occ > 2 ? 2 : occ);
    }
    CUtensorMap mapE, mapF, mapV;
    make_map(enc, &mapE, d_in[3], SKV, RK, RK);
    make_map(enc, &mapF, d_in[4], SKV, RK, RK);
    make_map(enc, &mapV, d_in[2], DH, (uint64_t)BH * SKV, FCH * TROWS);
    linformer_decode_kernel<<<grid, NTHREADS, SMEM_BYTES>>>(
        mapE, mapF, mapV, (const __nv_bfloat16*)d_in[0], (const __nv_bfloat16*)d_in[1], (const __nv_bfloat16*)d_in[2],
        (__nv_bfloat16*)d_out, (uint32_t)sms);
}
```
